```python
import torch

def _softmax(x, axis=-1):
    return torch.softmax(x, dim=axis)
def _gelu(x):
    return torch.nn.functional.gelu(x, approximate="tanh")
def _silu(x):
    return torch.nn.functional.silu(x)
def _sigmoid(x):
    return torch.sigmoid(x)
def _layernorm(x, axis=-1, eps=1e-5):
    m = x.mean(dim=axis, keepdim=True)
    v = x.var(dim=axis, keepdim=True, unbiased=False)
    return (x - m) / torch.sqrt(v + eps)
def _scatter_add(tgt, idx, src, axis=0):
    return tgt.clone().index_add_(axis, idx, src)
def _segment_sum(src, seg, n):
    out = torch.zeros((n,) + src.shape[1:], dtype=src.dtype)
    return out.index_add_(0, seg, src)
def _pad(x, pw):
    flat = tuple(v for pair in reversed(pw) for v in pair)
    return torch.nn.functional.pad(x, flat)

kernel_name = 'standalone__kv_cache_quant_int4_int2_kv_with_per_channel_or_per_token_scales__prompt'

def setup_inputs():

    _w = (lambda a: (lambda t: t.to(torch.bfloat16) if t.is_floating_point() else t)(torch.as_tensor(a)))
    B = 1
    Sq = 2048
    Skv = 2048
    Hq = 32
    Hkv = 32
    Dh = 128
    bits = 2
    G = 64
    if G <= 0 or G >= Skv:
        G = max(1, Skv // 2)
    Skv = (Skv // G) * G
    ngk = Skv // G
    qmax = (1 << bits) - 1
    return {
        "q": _w((lambda *s: torch.randn(*s, dtype=torch.bfloat16) * 1.6)(B, Hq, Sq, Dh)),
        "qk": _w(torch.randint(0, qmax + 1, (B, Hkv, Skv, Dh)).to(torch.int32)),
        "qv": _w(torch.randint(0, qmax + 1, (B, Hkv, Skv, Dh)).to(torch.int32)),
        "k_scales": _w(torch.abs((lambda *s: torch.randn(*s, dtype=torch.bfloat16) * 1.6)(B, Hkv, ngk, Dh)) * 0.05 + 0.02),
        "k_zeros": _w((lambda *s: torch.randn(*s, dtype=torch.bfloat16) * 1.6)(B, Hkv, ngk, Dh) + float(qmax) / 2.0),
        "v_scales": _w(torch.abs((lambda *s: torch.randn(*s, dtype=torch.bfloat16) * 0.05)(B, Hkv, Skv, 1)) * 0.05 + 0.02),
        "v_zeros": _w((lambda *s: torch.randn(*s, dtype=torch.bfloat16) * 0.05)(B, Hkv, Skv, 1) + float(qmax) / 2.0),
    }

def reference(q, qk, qv, k_scales, k_zeros, v_scales, v_zeros):
    B, Hq, Sq, Dh = q.shape
    Hkv, Skv = qk.shape[1], qk.shape[2]
    ngk = k_scales.shape[2]
    G = Skv // ngk
    ks = (lambda x, n, axis: torch.repeat_interleave(x, n, dim=axis))(k_scales, G, axis=2)
    kz = (lambda x, n, axis: torch.repeat_interleave(x, n, dim=axis))(k_zeros, G, axis=2)
    k = ((lambda x, dt: x.to(dt))(qk, q.dtype) - kz) * ks
    v = ((lambda x, dt: x.to(dt))(qv, q.dtype) - v_zeros) * v_scales
    rep = Hq // Hkv
    if rep > 1:
        k = (lambda x, n, axis: torch.repeat_interleave(x, n, dim=axis))(k, rep, axis=1)
        v = (lambda x, n, axis: torch.repeat_interleave(x, n, dim=axis))(v, rep, axis=1)
    scale = float(Dh) ** -0.5
    logits = torch.einsum("bhqd,bhkd->bhqk", q, k) * scale
    p = _softmax(logits, axis=-1)
    o = torch.einsum("bhqk,bhkd->bhqd", p, v)
    return o
```

```cpp
#include <cuda.h>
#include <cuda_runtime.h>
#include <cuda_bf16.h>
#include <stdint.h>

#define DEVINL __device__ __forceinline__

namespace {

constexpr int NH    = 32;
constexpr int SEQ   = 2048;
constexpr int DH    = 128;
constexpr int GRP   = 64;
constexpr int NGK   = SEQ / GRP;
constexpr int BM    = 128;
constexpr int BN    = 128;
constexpr int NBLK  = SEQ / BN;
constexpr int NQT   = SEQ / BM;
constexpr int NTILE = NH * NQT;
constexpr int IMG   = BN * DH * 2;
constexpr int NST   = 3;
constexpr int STAGE = 2 * IMG;

constexpr int SM_Q    = NST * STAGE;
constexpr int SM_BAR  = SM_Q + BM * DH * 2;
constexpr int SM_FLAG = SM_BAR + 64;
constexpr int SM_PUB  = SM_FLAG + 8 * 4 * 8;
constexpr int SM_TRACE = SM_PUB + 66 * 8;
constexpr int SM_ALLOC = SM_TRACE;
constexpr int NCTA   = 128;
constexpr int NWAVE  = NTILE / NCTA;
constexpr int NGROUP = NCTA / NQT;
constexpr int NSTEP  = NWAVE * NBLK;
constexpr int NPIECE = 2 * (NSTEP + 1);
constexpr int NFIRST = 6;

__device__ __align__(1024) uint8_t g_kimg[(size_t)NH * NBLK * IMG];
__device__ __align__(1024) uint8_t g_vimg[(size_t)NH * NBLK * IMG];
constexpr int READY_STRIDE = 96;
__device__ __align__(16) uint32_t g_ready[NGROUP * READY_STRIDE];
__device__ uint32_t g_done;

#define DQTRACE(it, i)
#define STARTCLK(i)
#define LOADCLK(i)
#define LTRACE(t, i)
#define LVAL(t, i, v)
#define TRACE(b, i)
#define CTATIME(i)
#define CTACLK(i)
DEVINL uint32_t smem_u32(const void* p) { return (uint32_t)__cvta_generic_to_shared(p); }

DEVINL void mbar_init(uint32_t bar, uint32_t cnt) {
    asm volatile("mbarrier.init.shared::cta.b64 [%0], %1;" ::"r"(bar), "r"(cnt) : "memory");
}
DEVINL void mbar_expect_tx(uint32_t bar, uint32_t bytes) {
    asm volatile("mbarrier.arrive.expect_tx.shared::cta.b64 _, [%0], %1;" ::"r"(bar), "r"(bytes) : "memory");
}
DEVINL void mbar_arrive(uint32_t bar) {
    asm volatile("mbarrier.arrive.shared::cta.b64 _, [%0];" ::"r"(bar) : "memory");
}
DEVINL void mbar_wait(uint32_t bar, uint32_t parity) {
    asm volatile(
        "{\n.reg .pred p;\n.reg .u32 c;\n"
        "mov.u32 c, 0;\n"
        "LAB_WAIT:\n"
        "mbarrier.try_wait.parity.shared::cta.b64 p, [%0], %1;\n"
        "@p bra DONE;\n"
        "add.u32 c, c, 1;\n"
        "setp.lt.u32 p, c, 0x8000;\n"
        "@p bra LAB_WAIT;\n"
        "DONE:\n}\n" ::"r"(bar), "r"(parity) : "memory");
}
DEVINL bool mbar_test(uint32_t bar, uint32_t parity) {
    uint32_t ok;
    asm volatile("{\n.reg .pred p;\nmbarrier.test_wait.parity.shared::cta.b64 p, [%1], %2;\nselp.u32 %0, 1, 0, p;\n}\n"
                 : "=r"(ok) : "r"(bar), "r"(parity) : "memory");
    return ok != 0;
}
DEVINL bool mbar_try(uint32_t bar, uint32_t parity, uint32_t ns) {
    uint32_t ok;
    asm volatile("{\n.reg .pred p;\nmbarrier.try_wait.parity.shared::cta.b64 p, [%1], %2, %3;\nselp.u32 %0, 1, 0, p;\n}\n"
                 : "=r"(ok) : "r"(bar), "r"(parity), "r"(ns) : "memory");
    return ok != 0;
}
DEVINL void bulk_g2s(uint32_t dst, const void* src, uint32_t bytes, uint32_t bar) {
    asm volatile("cp.async.bulk.shared::cluster.global.mbarrier::complete_tx::bytes [%0], [%1], %2, [%3];"
                 ::"r"(dst), "l"(src), "r"(bytes), "r"(bar) : "memory");
}
DEVINL void bulk_g2s_mc(uint32_t dst, const void* src, uint32_t bytes, uint32_t bar, uint16_t mask) {
    asm volatile("cp.async.bulk.shared::cluster.global.mbarrier::complete_tx::bytes.multicast::cluster [%0], [%1], %2, [%3], %4;"
                 ::"r"(dst), "l"(src), "r"(bytes), "r"(bar), "h"(mask) : "memory");
}
DEVINL uint32_t map_to_cta(uint32_t addr, uint32_t rank) {
    uint32_t r;
    asm("mapa.shared::cluster.u32 %0, %1, %2;" : "=r"(r) : "r"(addr), "r"(rank));
    return r;
}
DEVINL void mbar_arrive_cluster(uint32_t bar) {
    asm volatile("mbarrier.arrive.shared::cluster.b64 _, [%0];" ::"r"(bar) : "memory");
}
DEVINL void cp_async16(uint32_t dst, const void* src) {
    asm volatile("cp.async.cg.shared.global [%0], [%1], 16;" ::"r"(dst), "l"(src) : "memory");
}
DEVINL void cp_async_wait_all() { asm volatile("cp.async.wait_all;" ::: "memory"); }
DEVINL void tma_load_2d(uint32_t dst, const CUtensorMap* map, int c0, int c1, uint32_t bar) {
    asm volatile("cp.async.bulk.tensor.2d.shared::cluster.global.tile.mbarrier::complete_tx::bytes [%0], [%1, {%3, %4}], [%2];"
                 ::"r"(dst), "l"(map), "r"(bar), "r"(c0), "r"(c1) : "memory");
}
DEVINL void ldsm_x4(uint32_t& r0, uint32_t& r1, uint32_t& r2, uint32_t& r3, uint32_t addr) {
    asm volatile("ldmatrix.sync.aligned.m8n8.x4.shared.b16 {%0,%1,%2,%3}, [%4];"
                 : "=r"(r0), "=r"(r1), "=r"(r2), "=r"(r3) : "r"(addr) : "memory");
}
DEVINL void bar_sync(int id, int n) { asm volatile("bar.sync %0, %1;" ::"r"(id), "r"(n) : "memory"); }
DEVINL void bar_arrive(int id, int n) { asm volatile("bar.arrive %0, %1;" ::"r"(id), "r"(n) : "memory"); }

DEVINL uint32_t opaque(uint32_t x) { asm volatile("mov.u32 %0, %0;" : "+r"(x)); return x; }
DEVINL float ex2(float x) { float y; asm("ex2.approx.ftz.f32 %0, %1;" : "=f"(y) : "f"(x)); return y; }
DEVINL uint32_t pack_bf16(float lo, float hi) {
    uint32_t r; asm("cvt.rn.bf16x2.f32 %0, %1, %2;" : "=r"(r) : "f"(hi), "f"(lo)); return r;
}

#define WG_FENCE()  asm volatile("wgmma.fence.sync.aligned;" ::: "memory")
#define WG_COMMIT() asm volatile("wgmma.commit_group.sync.aligned;" ::: "memory")
#define WG_WAIT(n)  asm volatile("wgmma.wait_group.sync.aligned %0;" ::"n"(n) : "memory")

#define ACC64(d) \
  "+f"(d[0]),"+f"(d[1]),"+f"(d[2]),"+f"(d[3]),"+f"(d[4]),"+f"(d[5]),"+f"(d[6]),"+f"(d[7]), \
  "+f"(d[8]),"+f"(d[9]),"+f"(d[10]),"+f"(d[11]),"+f"(d[12]),"+f"(d[13]),"+f"(d[14]),"+f"(d[15]), \
  "+f"(d[16]),"+f"(d[17]),"+f"(d[18]),"+f"(d[19]),"+f"(d[20]),"+f"(d[21]),"+f"(d[22]),"+f"(d[23]), \
  "+f"(d[24]),"+f"(d[25]),"+f"(d[26]),"+f"(d[27]),"+f"(d[28]),"+f"(d[29]),"+f"(d[30]),"+f"(d[31]), \
  "+f"(d[32]),"+f"(d[33]),"+f"(d[34]),"+f"(d[35]),"+f"(d[36]),"+f"(d[37]),"+f"(d[38]),"+f"(d[39]), \
  "+f"(d[40]),"+f"(d[41]),"+f"(d[42]),"+f"(d[43]),"+f"(d[44]),"+f"(d[45]),"+f"(d[46]),"+f"(d[47]), \
  "+f"(d[48]),"+f"(d[49]),"+f"(d[50]),"+f"(d[51]),"+f"(d[52]),"+f"(d[53]),"+f"(d[54]),"+f"(d[55]), \
  "+f"(d[56]),"+f"(d[57]),"+f"(d[58]),"+f"(d[59]),"+f"(d[60]),"+f"(d[61]),"+f"(d[62]),"+f"(d[63])
#define REGS64 \
  "{%0,%1,%2,%3,%4,%5,%6,%7,%8,%9,%10,%11,%12,%13,%14,%15,%16,%17,%18,%19,%20,%21,%22,%23,%24,%25," \
  "%26,%27,%28,%29,%30,%31,%32,%33,%34,%35,%36,%37,%38,%39,%40,%41,%42,%43,%44,%45,%46,%47,%48,%49," \
  "%50,%51,%52,%53,%54,%55,%56,%57,%58,%59,%60,%61,%62,%63}"

template <int TRANS_B>
DEVINL void wgmma_rs(float (&d)[64], uint32_t a0, uint32_t a1, uint32_t a2, uint32_t a3, uint64_t db, int scale_d) {
    asm volatile(
        "{\n.reg .pred p;\nsetp.ne.b32 p, %69, 0;\n"
        "wgmma.mma_async.sync.aligned.m64n128k16.f32.bf16.bf16 " REGS64
        ", {%64,%65,%66,%67}, %68, p, 1, 1, %70;\n}\n"
        : ACC64(d)
        : "r"(a0), "r"(a1), "r"(a2), "r"(a3), "l"(db), "r"(scale_d), "n"(TRANS_B));
}
DEVINL void reg_fence(float (&d)[64]) {
#pragma unroll
    for (int i = 0; i < 64; ++i) asm volatile("" : "+f"(d[i])::"memory");
}
DEVINL void reg_fence(uint32_t (&d)[32]) {
#pragma unroll
    for (int i = 0; i < 32; ++i) asm volatile("" : "+r"(d[i])::"memory");
}

DEVINL uint64_t make_desc(uint32_t addr, uint32_t lbo, uint32_t sbo) {
    return (uint64_t)((addr & 0x3FFFF) >> 4) | ((uint64_t)(lbo >> 4) << 16) | ((uint64_t)(sbo >> 4) << 32) |
           ((uint64_t)1 << 62);
}

DEVINL __nv_bfloat162 as_bf162(uint32_t u) { return *reinterpret_cast<__nv_bfloat162*>(&u); }
DEVINL uint32_t as_u32(__nv_bfloat162 v) { return *reinterpret_cast<uint32_t*>(&v); }

DEVINL uint32_t dq2(int c0, int c1, uint32_t z2, uint32_t s2) {
    __nv_bfloat162 v = as_bf162(pack_bf16((float)c0, (float)c1));
    v = __hsub2(v, as_bf162(z2));
    v = __hmul2(v, as_bf162(s2));
    return as_u32(v);
}

constexpr float SCALE_LOG2E = 0.08838834764831845f * 1.4426950408889634f;
constexpr uint32_t SCALE_HI2 = 0x3E033E03u;
constexpr uint32_t SCALE_LO2 = 0xB9D8B9D8u;

DEVINL uint32_t scale_k2(uint32_t k2) {
    const __nv_bfloat162 k = as_bf162(k2);
    return as_u32(__hfma2(k, as_bf162(SCALE_HI2), __hmul2(k, as_bf162(SCALE_LO2))));
}

struct Params {
    const __nv_bfloat16* q;
    const int* qk;
    const int* qv;
    const __nv_bfloat16* ks;
    const __nv_bfloat16* kz;
    const __nv_bfloat16* vs;
    const __nv_bfloat16* vz;
    __nv_bfloat16* out;
};

struct Piece {
    int ck[16];
    int cv[16];
    uint32_t ks[2], kz[2], vs, vz;
};
DEVINL uint32_t piece_token(uint32_t m, uint32_t cta) {
    return (cta / NQT) * (NSTEP * BN) + (cta % NQT) * 8 + (m >> 1) * BN + (m & 1) * 4;
}
struct LaneOff { uint32_t src, dst; };
DEVINL LaneOff lane_offsets(uint32_t lane) {
    LaneOff o;
    o.src = (lane * 16) | ((((lane >> 4) * DH + ((lane >> 2) & 3) * 16 + (lane & 3)) * 8) << 16);
    o.dst = ((lane >> 4) * (IMG / 2) + (lane & 1) * 8 + (((lane & 15) >> 1) << 4)) |
            (((lane >> 4) * 256 + ((lane >> 3) & 1) * (IMG / 2) + (((lane & 7) ^ ((lane >> 4) * 2)) << 4)) << 16);
    return o;
}
DEVINL const uint8_t* bytes(const void* p) { return reinterpret_cast<const uint8_t*>(p); }
DEVINL uint32_t image_offset(uint32_t ht) { return ((ht >> 7) * IMG + (ht & 127) * 128) | ((ht & 4) << 4); }

DEVINL void piece_load_k(const Params& prm, Piece& pc, uint32_t ht, uint32_t src) {
    const uint32_t l16 = src & 0xFFFFu;
    const int4* p = reinterpret_cast<const int4*>(bytes(prm.qk) + (ht * (DH * 4) + l16));
#pragma unroll
    for (int r = 0; r < 4; ++r) {
        const int4 v = __ldcs(p + r * (DH / 4));
        pc.ck[4 * r] = v.x; pc.ck[4 * r + 1] = v.y; pc.ck[4 * r + 2] = v.z; pc.ck[4 * r + 3] = v.w;
    }
    const uint32_t so = (ht / GRP) * (DH * 2) + (l16 >> 1);
    const uint2 s2 = __ldg(reinterpret_cast<const uint2*>(bytes(prm.ks) + so));
    const uint2 z2 = __ldg(reinterpret_cast<const uint2*>(bytes(prm.kz) + so));
    pc.ks[0] = s2.x; pc.ks[1] = s2.y; pc.kz[0] = z2.x; pc.kz[1] = z2.y;
}
DEVINL void piece_store_k(const Piece& pc, uint32_t ht, uint32_t dst) {
    uint64_t a = reinterpret_cast<uint64_t>(g_kimg) + (image_offset(ht) ^ (dst & 0xFFFFu));
#pragma unroll
    for (int r = 0; r < 4; ++r) {
        const uint32_t x = scale_k2(dq2(pc.ck[4 * r], pc.ck[4 * r + 1], pc.kz[0], pc.ks[0]));
        const uint32_t y = scale_k2(dq2(pc.ck[4 * r + 2], pc.ck[4 * r + 3], pc.kz[1], pc.ks[1]));
        asm volatile("st.global.v2.u32 [%0], {%1, %2};" ::"l"(a + r * 128), "r"(x), "r"(y) : "memory");
        a ^= (uint64_t)(((r ^ (r + 1)) & 3) << 4);
    }
}
DEVINL void piece_load_v(const Params& prm, Piece& pc, uint32_t ht, uint32_t src) {
    const int2* p = reinterpret_cast<const int2*>(bytes(prm.qv) + ((ht - BN) * (DH * 4) + (src >> 16)));
#pragma unroll
    for (int it = 0; it < 2; ++it)
#pragma unroll
        for (int t = 0; t < 4; ++t) {
            const int2 v = __ldcs(p + it * (DH / 2) + t * 4);
            pc.cv[it * 8 + 2 * t] = v.x; pc.cv[it * 8 + 2 * t + 1] = v.y;
        }
    const uint32_t so = (ht - BN) * 2 + ((src >> 6) & 4);
    pc.vs = __ldg(reinterpret_cast<const uint32_t*>(bytes(prm.vs) + so));
    pc.vz = __ldg(reinterpret_cast<const uint32_t*>(bytes(prm.vz) + so));
}
DEVINL void piece_store_v(const Piece& pc, uint32_t ht, uint32_t dst) {
    uint64_t a = (reinterpret_cast<uint64_t>(g_vimg) - IMG) + (image_offset(ht) ^ (dst >> 16));
#pragma unroll
    for (int it = 0; it < 2; ++it) {
        const uint32_t sel = it ? 0x3232u : 0x1010u;
        const uint32_t s2 = __byte_perm(pc.vs, 0, sel), z2 = __byte_perm(pc.vz, 0, sel);
        const uint32_t x = dq2(pc.cv[it * 8 + 0], pc.cv[it * 8 + 1], z2, s2);
        const uint32_t y = dq2(pc.cv[it * 8 + 2], pc.cv[it * 8 + 3], z2, s2);
        const uint32_t z = dq2(pc.cv[it * 8 + 4], pc.cv[it * 8 + 5], z2, s2);
        const uint32_t w = dq2(pc.cv[it * 8 + 6], pc.cv[it * 8 + 7], z2, s2);
        asm volatile("st.global.v4.u32 [%0], {%1, %2, %3, %4};" ::"l"(a + it * 128), "r"(x), "r"(y), "r"(z), "r"(w) : "memory");
        a ^= 0x10;
    }
}
DEVINL void piece_prefetch(const Params& prm, uint32_t ht, uint32_t src) {
    const uint8_t* base = (src & 0x100u) ? bytes(prm.qv) - BN * DH * 4 : bytes(prm.qk);
    asm volatile("prefetch.global.L2 [%0];" ::"l"(base + (ht * (DH * 4) + ((src & 0xF0u) << 3))));
}
DEVINL void piece_done(uint32_t sbase, uint32_t m, uint32_t src) {
    __syncwarp();
    if ((src & 0xFFFFu) == 0) mbar_arrive(sbase + SM_PUB + 8 * (m >> 1));
    __syncwarp();
}
DEVINL void piece_simple(const Params& prm, uint32_t sbase, uint32_t m, uint32_t cta, uint32_t lane) {
    Piece pc;
    const LaneOff lo = lane_offsets(lane);
    const uint32_t ht = piece_token(m, cta);
    piece_load_k(prm, pc, ht, lo.src);
    if (m >= 2) piece_load_v(prm, pc, ht, lo.src);
    piece_store_k(pc, ht, lo.dst);
    if (m >= 2) piece_store_v(pc, ht, lo.dst);
    piece_done(sbase, m, lo.src);
}

#define SUM_LAG 1
#define POLL_LEAD 4
#define PUB_LEAD 7
#define PUB_FIRST 1
#define QPOS 1
#define QDELAY 200

DEVINL void load_q_regs(uint32_t sq, uint32_t (&qr)[32], int lane) {
    const int row = ((lane >> 3) & 1) * 8 + (lane & 7);
    const uint32_t a0 = opaque(sq + row * 128 + (((lane >> 4) ^ (lane & 7)) << 4));
#pragma unroll
    for (int s = 0; s < 8; ++s)
        ldsm_x4(qr[4 * s], qr[4 * s + 1], qr[4 * s + 2], qr[4 * s + 3], (a0 ^ ((s & 3) << 5)) + (s >> 2) * (BM * 128));
}

DEVINL void issue_qk(float (&s)[64], const uint32_t (&qr)[32], uint32_t kaddr) {
    const uint64_t d0 = make_desc(kaddr, 16, 1024);
#pragma unroll
    for (int k = 0; k < 8; ++k) {
        const uint64_t d = d0 + (uint64_t)(((k >> 2) * (IMG / 2) + (k & 3) * 32) >> 4);
        wgmma_rs<0>(s, qr[4 * k], qr[4 * k + 1], qr[4 * k + 2], qr[4 * k + 3], d, k > 0);
    }
}
DEVINL void issue_pv(float (&o)[64], const uint32_t (&p)[32], uint32_t vaddr, int accumulate) {
    const uint64_t d0 = make_desc(vaddr, IMG / 2, 1024);
#pragma unroll
    for (int k = 0; k < 8; ++k) {
        const uint64_t d = d0 + (uint64_t)((k * 2048) >> 4);
        wgmma_rs<1>(o, p[4 * k], p[4 * k + 1], p[4 * k + 2], p[4 * k + 3], d, k > 0 ? 1 : accumulate);
    }
}

DEVINL uint32_t finish_rows(float l0, float l1, float& i0, float& i1) {
    l0 += __shfl_xor_sync(0xffffffffu, l0, 1);
    l1 += __shfl_xor_sync(0xffffffffu, l1, 1);
    l0 += __shfl_xor_sync(0xffffffffu, l0, 2);
    l1 += __shfl_xor_sync(0xffffffffu, l1, 2);
    asm("rcp.approx.ftz.f32 %0, %1;" : "=f"(i0) : "f"(l0));
    asm("rcp.approx.ftz.f32 %0, %1;" : "=f"(i1) : "f"(l1));
    const float LO = 9.5367431640625e-07f, HI = 1.2676506e30f;
    return (l0 >= LO && l0 < HI ? 0u : 1u) | (l1 >= LO && l1 < HI ? 0u : 2u);
}
DEVINL uint32_t write_out(const float (&o)[64], float i0, float i1, __nv_bfloat16* __restrict__ out, int tile, int wg,
                          int warp, int lane) {
    uint4* dst = reinterpret_cast<uint4*>(out + ((size_t)tile * BM + wg * 64 + warp * 16 + (lane >> 2)) * DH) + (lane & 3);
    uint32_t c0 = 0, c1 = 0;
#pragma unroll
    for (int i = 0; i < 4; ++i) {
        uint32_t a[4], b[4];
#pragma unroll
        for (int j = 0; j < 4; ++j) {
            a[j] = pack_bf16(o[16 * i + 4 * j] * i0, o[16 * i + 4 * j + 1] * i0);
            b[j] = pack_bf16(o[16 * i + 4 * j + 2] * i1, o[16 * i + 4 * j + 3] * i1);
            asm("max.NaN.xorsign.abs.bf16x2 %0, %0, %1;" : "+r"(c0) : "r"(a[j]));
            asm("max.NaN.xorsign.abs.bf16x2 %0, %0, %1;" : "+r"(c1) : "r"(b[j]));
        }
        __stcs(dst + i * 4, make_uint4(a[0], a[1], a[2], a[3]));
        __stcs(dst + i * 4 + 8 * (DH * 2 / 16), make_uint4(b[0], b[1], b[2], b[3]));
    }
    const bool bad0 = (c0 & 0x7F80u) == 0x7F80u || (c0 & 0x7F800000u) == 0x7F800000u;
    const bool bad1 = (c1 & 0x7F80u) == 0x7F80u || (c1 & 0x7F800000u) == 0x7F800000u;
    return (bad0 ? 1u : 0u) | (bad1 ? 2u : 0u);
}

DEVINL void softmax_exp(float (&s)[64], float& l0, float& l1) {
#pragma unroll
    for (int j = 0; j < 16; ++j) {
        asm volatile("ex2.approx.ftz.f32 %0, %0;" : "+f"(s[4 * j]));
        asm volatile("ex2.approx.ftz.f32 %0, %0;" : "+f"(s[4 * j + 2]));
        asm volatile("ex2.approx.ftz.f32 %0, %0;" : "+f"(s[4 * j + 1]));
        asm volatile("ex2.approx.ftz.f32 %0, %0;" : "+f"(s[4 * j + 3]));
        if (SUM_LAG > 0 && j >= SUM_LAG) {
            const int i = j - SUM_LAG;
            asm volatile("add.f32 %0, %0, %1;" : "+f"(l0) : "f"(s[4 * i]));
            asm volatile("add.f32 %0, %0, %1;" : "+f"(l1) : "f"(s[4 * i + 2]));
            asm volatile("add.f32 %0, %0, %1;" : "+f"(l0) : "f"(s[4 * i + 1]));
            asm volatile("add.f32 %0, %0, %1;" : "+f"(l1) : "f"(s[4 * i + 3]));
        }
    }
}
DEVINL void pack_p(uint32_t (&p)[32], const float (&s)[64], float& l0, float& l1) {
#pragma unroll
    for (int j = 0; j < 16; ++j) {
        asm volatile("cvt.rn.bf16x2.f32 %0, %1, %2;" : "=r"(p[2 * j]) : "f"(s[4 * j + 1]), "f"(s[4 * j]));
        asm volatile("cvt.rn.bf16x2.f32 %0, %1, %2;" : "=r"(p[2 * j + 1]) : "f"(s[4 * j + 3]), "f"(s[4 * j + 2]));
        if (SUM_LAG == 0 || j >= 16 - SUM_LAG) {
            asm volatile("add.f32 %0, %0, %1;" : "+f"(l0) : "f"(s[4 * j]));
            asm volatile("add.f32 %0, %0, %1;" : "+f"(l1) : "f"(s[4 * j + 2]));
            asm volatile("add.f32 %0, %0, %1;" : "+f"(l0) : "f"(s[4 * j + 1]));
            asm volatile("add.f32 %0, %0, %1;" : "+f"(l1) : "f"(s[4 * j + 3]));
        }
    }
}

__device__ __noinline__ void exact_row(const __nv_bfloat16* __restrict__ q, const int* __restrict__ qk,
                                       const int* __restrict__ qv, const __nv_bfloat16* __restrict__ ks,
                                       const __nv_bfloat16* __restrict__ kz, const __nv_bfloat16* __restrict__ vs,
                                       const __nv_bfloat16* __restrict__ vz, __nv_bfloat16* __restrict__ out, int h,
                                       int row, int lane) {
    const uint2 qw = *reinterpret_cast<const uint2*>(q + ((size_t)h * SEQ + row) * DH + 4 * lane);
    const float2 q01 = __bfloat1622float2(as_bf162(qw.x)), q23 = __bfloat1622float2(as_bf162(qw.y));
    float m = -INFINITY, l = 0.f, o0 = 0.f, o1 = 0.f, o2 = 0.f, o3 = 0.f;
    for (int t = 0; t < SEQ; ++t) {
        const size_t so = ((size_t)h * NGK + t / GRP) * DH + 4 * lane;
        const uint2 sc = *reinterpret_cast<const uint2*>(ks + so), zz = *reinterpret_cast<const uint2*>(kz + so);
        const int4 ck = *(reinterpret_cast<const int4*>(qk + ((size_t)h * SEQ + t) * DH) + lane);
        const float2 k01 = __bfloat1622float2(as_bf162(dq2(ck.x, ck.y, zz.x, sc.x)));
        const float2 k23 = __bfloat1622float2(as_bf162(dq2(ck.z, ck.w, zz.y, sc.y)));
        float d = q01.x * k01.x + q01.y * k01.y + q23.x * k23.x + q23.y * k23.y;
#pragma unroll
        for (int x = 16; x > 0; x >>= 1) d += __shfl_xor_sync(0xffffffffu, d, x);
        d *= SCALE_LOG2E;
        const float mn = fmaxf(m, d);
        const float a = exp2f(m - mn), pr = exp2f(d - mn);
        m = mn;
        const uint32_t sv = (uint32_t)__bfloat16_as_ushort(vs[(size_t)h * SEQ + t]) * 0x10001u;
        const uint32_t zv = (uint32_t)__bfloat16_as_ushort(vz[(size_t)h * SEQ + t]) * 0x10001u;
        const int4 cv = *(reinterpret_cast<const int4*>(qv + ((size_t)h * SEQ + t) * DH) + lane);
        const float2 v01 = __bfloat1622float2(as_bf162(dq2(cv.x, cv.y, zv, sv)));
        const float2 v23 = __bfloat1622float2(as_bf162(dq2(cv.z, cv.w, zv, sv)));
        l = l * a + pr;
        o0 = o0 * a + pr * v01.x; o1 = o1 * a + pr * v01.y;
        o2 = o2 * a + pr * v23.x; o3 = o3 * a + pr * v23.y;
    }
    const float inv = 1.0f / l;
    uint2 w;
    w.x = pack_bf16(o0 * inv, o1 * inv);
    w.y = pack_bf16(o2 * inv, o3 * inv);
    *reinterpret_cast<uint2*>(out + ((size_t)h * SEQ + row) * DH + 4 * lane) = w;
}

enum { STEP_REG = 0, STEP_LASTQK = 1, STEP_NEXT = 2 };

template <int CL>
__global__ void __launch_bounds__(384, 1) attn_kernel(const Params prm, const __grid_constant__ CUtensorMap qmap) {
    extern __shared__ __align__(1024) uint8_t smem_raw[];
    const uint32_t sbase = smem_u32(smem_raw);
    const uint32_t bar_full  = sbase + SM_BAR;
    const uint32_t bar_empty = bar_full + 8 * NST;
    const uint32_t bar_qfull = bar_empty + 8 * NST;
    const uint32_t bar_qempty = bar_qfull + 8;
    const uint32_t sm_flag = sbase + SM_FLAG;

    const int tid = threadIdx.x;
    STARTCLK(0);
    const int warp_idx = __shfl_sync(0xffffffffu, tid >> 5, 0);
    const int wgi = warp_idx >> 2;
    const int cta = blockIdx.x;
    const int tile0 = (cta / NQT) * (NWAVE * NQT) + cta % NQT;
    constexpr int ntiles = NWAVE;

    if (tid == 0) {
        if (sbase & 1023u) __trap();
        for (int s = 0; s < NST; ++s) { mbar_init(bar_full + 8 * s, 1); mbar_init(bar_empty + 8 * s, 8 * CL); }
        mbar_init(bar_qfull, 1);
        mbar_init(bar_qempty, 8);
        for (int T = 0; T <= NSTEP; ++T) mbar_init(sbase + SM_PUB + 8 * T, 2);
        asm volatile("fence.mbarrier_init.release.cluster;" ::: "memory");
        asm volatile("fence.proxy.async.shared::cta;" ::: "memory");
    }
    __syncthreads();
    if (CL > 1) asm volatile("barrier.cluster.arrive.relaxed.aligned;" ::: "memory");
    STARTCLK(1);

    if (wgi == 0) {
        asm volatile("setmaxnreg.dec.sync.aligned.u32 56;");
        const int lane = tid & 31;
        if (warp_idx == 0) {
            auto load_q = [&](int ti) {
                if (lane == 0) {
                    const int row0 = (tile0 + ti * NQT) * BM;
                    mbar_expect_tx(bar_qfull, BM * DH * 2);
                    tma_load_2d(sbase + SM_Q, &qmap, 0, row0, bar_qfull);
                    tma_load_2d(sbase + SM_Q + BM * 128, &qmap, 64, row0, bar_qfull);
                }
            };
            uint32_t* ready = g_ready + (cta / NQT) * READY_STRIDE;
            constexpr int nb = ntiles * NBLK;
            int ready_upto = 0;
            int tp = 0;
            int q_next = 1;
            int st = 0, ph = 1;
            auto poll = [&](int from) {
                uint32_t v;
                asm volatile("ld.acquire.gpu.global.u32 %0, [%1];" : "=r"(v) : "l"(ready + from + lane) : "memory");
                const uint32_t done = __ballot_sync(0xffffffffu, v >= NQT);
                ready_upto = from + __clz(__brev(~done));
                __syncwarp();
                asm volatile("fence.proxy.async.global;" ::: "memory");
            };
            LOADCLK(8);
            while (tp < NFIRST / 2) {
                mbar_wait(sbase + SM_PUB + 8 * tp, 0);
                const bool done = tp + lane < NFIRST / 2 && mbar_test(sbase + SM_PUB + 8 * (tp + lane), 0);
                const int n = __clz(__brev(~__ballot_sync(0xffffffffu, done)));
                if (tp == 0) LOADCLK(5);
                if (lane < n) {
                    asm volatile("fence.acq_rel.gpu;" ::: "memory");
                    asm volatile("red.relaxed.gpu.global.add.u32 [%0], 1;" ::"l"(ready + tp + lane) : "memory");
                }
                __syncwarp();
                if (tp == 0) LOADCLK(6);
                tp += n > 0 ? n : 1;
            }
            if (CL > 1) asm volatile("barrier.cluster.wait.acquire.aligned;" ::: "memory");
            for (int t = 0; t <= nb; ++t) {
                LTRACE(t, 0);
                for (int spins = 0; t >= ready_upto && spins < (1 << 18); ++spins) {
                    poll(t);
                    if (t >= ready_upto) __nanosleep(40);
                }
                if (t == 0) LOADCLK(10);
                LTRACE(t, 1);
                mbar_wait(bar_empty + 8 * st, ph);
                LTRACE(t, 2);
                if (lane == 0) {
                    const size_t blk = (size_t)((cta / NQT) * NSTEP + t) * IMG;
                    mbar_expect_tx(bar_full + 8 * st, (t > 0 && t < nb) ? 2 * IMG : IMG);
                    if (CL == 1) {
                        if (t < nb) bulk_g2s(sbase + st * STAGE, g_kimg + blk, IMG, bar_full + 8 * st);
                        if (t > 0) bulk_g2s(sbase + st * STAGE + IMG, g_vimg + blk - IMG, IMG, bar_full + 8 * st);
                    } else {
                        constexpr int PART = STAGE / CL;
                        const int off = (cta % CL) * PART;
                        const bool is_v = off >= IMG;
                        if (is_v ? t > 0 : t < nb)
                            bulk_g2s_mc(sbase + st * STAGE + off, (is_v ? g_vimg + blk - 2 * IMG : g_kimg + blk) + off, PART,
                                        bar_full + 8 * st, (uint16_t)((1 << CL) - 1));
                    }
                }
                __syncwarp();
                if (++st == NST) { st = 0; ph ^= 1; }
                LTRACE(t, 3);
                if (q_next < ntiles && t > (q_next - 1) * NBLK + 4) {
                    mbar_wait(bar_qempty, (q_next - 1) & 1);
                    load_q(q_next);
                    ++q_next;
                }
                if (ready_upto <= t + POLL_LEAD && ready_upto <= nb) poll(ready_upto);
                LTRACE(t, 4);
                LTRACE(t, 5);
                LVAL(t, 6, tp);
                LVAL(t, 7, ready_upto);
            }
            uint32_t old = 0;
            if (lane == 0) old = atomicAdd(&g_done, 1u);
            old = __shfl_sync(0xffffffffu, old, 0);
            if (old == (uint32_t)NCTA - 1) {
                for (int i = lane; i < NGROUP * READY_STRIDE / 4; i += 32) reinterpret_cast<uint4*>(g_ready)[i] = make_uint4(0, 0, 0, 0);
                if (lane == 0) g_done = 0;
            }
        } else {
            piece_simple(prm, sbase, warp_idx - 1, cta, lane);
            uint32_t m = warp_idx - 1 + NFIRST;
            const LaneOff lo = lane_offsets(lane);
            Piece pc;
            uint32_t ht = piece_token(m, cta);
            uint32_t ht1 = ht + ((m & 1) ? 2 * BN - 4 : BN + 4);
            piece_load_k(prm, pc, ht, lo.src);
            piece_load_v(prm, pc, ht, lo.src);
            piece_prefetch(prm, ht1, lo.src);
            int dqit = 0;
            while (true) {
                DQTRACE(dqit, 0);
                if (m + 6 < 2 * NSTEP) piece_prefetch(prm, ht + 3 * BN, opaque(lo.src));
                if ((m & 31) == 8 && m < 2 * NSTEP - 32) {
                    const uint8_t* qp = bytes(prm.q) + (size_t)(tile0 + ((m >> 5) + 1) * NQT) * (BM * DH * 2) + lane * 128;
#pragma unroll
                    for (int i = 0; i < 8; ++i) asm volatile("prefetch.global.L2 [%0];" ::"l"(qp + i * 4096));
                }
                if (m < 2 * NSTEP) piece_store_k(pc, ht, opaque(lo.dst));
                if (m + 3 < 2 * NSTEP) piece_load_k(prm, pc, ht1, opaque(lo.src));
                mbar_wait(sbase + SM_PUB, 0);
                DQTRACE(dqit, 1);
                piece_store_v(pc, ht, opaque(lo.dst));
                piece_done(sbase, m, opaque(lo.src));
                if (m + 3 < NPIECE) piece_load_v(prm, pc, ht1, opaque(lo.src));
                if (m & 1) {
                    mbar_wait(sbase + SM_PUB + 8 * (m >> 1), 0);
                    if ((opaque(lo.src) & 0xFFFFu) == 0) {
                        asm volatile("fence.acq_rel.gpu;" ::: "memory");
                        asm volatile("red.relaxed.gpu.global.add.u32 [%0], 1;" ::"l"(g_ready + (cta / NQT) * READY_STRIDE + (m >> 1)) : "memory");
                    }
                    __syncwarp();
                }
                if (m + 3 >= NPIECE) break;
                DQTRACE(dqit, 2);
                DQTRACE(dqit, 3);
                ++dqit;
                m += 3;
                const uint32_t next = ht + 3 * BN;
                ht = ht1;
                ht1 = next;
            }
            CTACLK(7);
        }
    } else {
        asm volatile("setmaxnreg.inc.sync.aligned.u32 224;");
        const int wg = wgi - 1;
        const int warp = warp_idx & 3, lane = tid & 31;
        const uint32_t sq = sbase + SM_Q + (wg * 64 + warp * 16) * 128;
        const int my_turn = 1 + wg, other_turn = 2 - wg;
        const uint32_t rel_bar = CL > 1 ? map_to_cta(bar_empty, lane % CL) : bar_empty;
        auto release = [&](uint32_t stage) {
            if (lane < CL) { if (CL > 1) mbar_arrive_cluster(rel_bar + 8 * stage); else mbar_arrive(rel_bar + 8 * stage); }
        };

        STARTCLK(2);
        if (wg == 1 && warp < 3) piece_simple(prm, sbase, 3 + warp, cta, lane);
        STARTCLK(3);

        float s[64], o[64];
        uint32_t p[32], qr[32];
        float l0, l1;
        uint32_t st = 0, ph = 0;

        {
            __nanosleep(QDELAY);
            const uint8_t* src = reinterpret_cast<const uint8_t*>(prm.q + ((size_t)tile0 * BM + wg * 64 + warp * 16 + (lane >> 4)) * DH) + (lane & 15) * 16;
            const uint32_t dst = sq + (lane >> 4) * 128 + ((lane >> 3) & 1) * (BM * 128) + (((lane & 7) ^ (lane >> 4)) << 4);
#pragma unroll
            for (int it = 0; it < 8; ++it)
                cp_async16((dst ^ (((2 * it) & 7) << 4)) + it * 256, src + it * 512);
            cp_async_wait_all();
            __syncwarp();
        }
        STARTCLK(4);
        load_q_regs(sq, qr, lane);
        __syncwarp();
        if (lane == 0) mbar_arrive(bar_qempty);

        if (CL > 1) asm volatile("barrier.cluster.wait.acquire.aligned;" ::: "memory");
        CTACLK(2);
        STARTCLK(7);
        if (wg == 0) bar_arrive(my_turn, 256);

        mbar_wait(bar_full + 8 * st, ph);
        CTACLK(3);
        STARTCLK(11);
        bar_sync(my_turn, 256);
        WG_FENCE();
        issue_qk(s, qr, sbase + st * STAGE);
        WG_COMMIT();
        bar_arrive(other_turn, 256);
        WG_WAIT(0);
        reg_fence(s);
        release(st);
        if (++st == NST) { st = 0; ph ^= 1; }
        l0 = l1 = 0.f;
        softmax_exp(s, l0, l1);
        pack_p(p, s, l0, l1);
        mbar_wait(bar_full + 8 * st, ph);

        int tb = 0;
        auto step = [&](auto mode_c, int accumulate, int ti, bool rel) {
            constexpr int MODE = decltype(mode_c)::value;
            TRACE(tb, 0);
            bar_sync(my_turn, 256);
            TRACE(tb, 2);
            WG_FENCE();
            issue_qk(s, qr, sbase + st * STAGE);
            WG_COMMIT();
            issue_pv(o, p, sbase + st * STAGE + IMG, accumulate);
            WG_COMMIT();
            bar_arrive(other_turn, 256);
            TRACE(tb, 3);
            WG_WAIT(1);
            reg_fence(s);
            TRACE(tb, 4);
            float inv0 = 0.f, inv1 = 0.f;
            uint32_t bad = 0;
            if (MODE == STEP_NEXT) {
                bad = finish_rows(l0, l1, inv0, inv1);
                l0 = l1 = 0.f;
            }
            softmax_exp(s, l0, l1);
            if (MODE == STEP_LASTQK) {
                if (ti + 1 < ntiles) {
                    mbar_wait(bar_qfull, ti & 1);
                    load_q_regs(sq, qr, lane);
                }
            }
            const uint32_t cur = st;
            if (++st == NST) { st = 0; ph ^= 1; }
            mbar_wait(bar_full + 8 * st, ph);
            TRACE(tb, 5);
            WG_WAIT(0);
            reg_fence(o);
            TRACE(tb, 6);
            if (rel) release(cur);
            if (MODE == STEP_NEXT) {
                bad |= write_out(o, inv0, inv1, prm.out, tile0 + ti * NQT, wg, warp, lane);
                const uint32_t m0 = __ballot_sync(0xffffffffu, bad & 1), m1 = __ballot_sync(0xffffffffu, bad & 2);
                if (lane == 0)
                    asm volatile("st.shared.v2.u32 [%0], {%1, %2};" ::"r"(sm_flag + ((wg * 4 + warp) * 4 + ti) * 8), "r"(m0), "r"(m1) : "memory");
            }
            pack_p(p, s, l0, l1);
            if (MODE == STEP_LASTQK) {
                if (ti + 1 < ntiles) {
                    __syncwarp();
                    if (lane == 0) mbar_arrive(bar_qempty);
                }
            }
            TRACE(tb, 7);
        };
        struct M0 { enum { value = STEP_REG }; };
        struct M1 { enum { value = STEP_LASTQK }; };
        struct M2 { enum { value = STEP_NEXT }; };

        for (int ti = 0; ti < ntiles; ++ti) {
#pragma unroll 1
            for (int j = 1; j < NBLK - 1; ++j) { step(M0{}, j != 1, ti, ti + 1 < ntiles || j < NBLK - 2); ++tb; }
            step(M1{}, 1, ti, ti + 1 < ntiles); ++tb;
            if (ti + 1 < ntiles) { step(M2{}, 1, ti, true); ++tb; }
        }

        CTACLK(4);
        bar_sync(my_turn, 256);
        WG_FENCE();
        issue_pv(o, p, sbase + st * STAGE + IMG, 1);
        WG_COMMIT();
        if (wg == 0) bar_arrive(other_turn, 256);
        float inv0, inv1;
        uint32_t bad = finish_rows(l0, l1, inv0, inv1);
        WG_WAIT(0);
        reg_fence(o);
        {
            bad |= write_out(o, inv0, inv1, prm.out, tile0 + (ntiles - 1) * NQT, wg, warp, lane);
            const uint32_t m0 = __ballot_sync(0xffffffffu, bad & 1), m1 = __ballot_sync(0xffffffffu, bad & 2);
            if (lane == 0)
                asm volatile("st.shared.v2.u32 [%0], {%1, %2};" ::"r"(sm_flag + ((wg * 4 + warp) * 4 + ntiles - 1) * 8), "r"(m0), "r"(m1) : "memory");
        }
        __syncwarp();
        for (int ti = 0; ti < ntiles; ++ti) {
            uint32_t m0, m1;
            asm volatile("ld.shared.v2.u32 {%0, %1}, [%2];" : "=r"(m0), "=r"(m1) : "r"(sm_flag + ((wg * 4 + warp) * 4 + ti) * 8) : "memory");
            if (m0 | m1) {
                const int tile = tile0 + ti * NQT;
                for (int r = 0; r < 16; ++r) {
                    const uint32_t m = (r < 8 ? m0 : m1) >> ((r & 7) * 4);
                    if (m & 0xF)
                        exact_row(prm.q, prm.qk, prm.qv, prm.ks, prm.kz, prm.vs, prm.vz, prm.out, tile / NQT,
                                  (tile % NQT) * BM + wg * 64 + warp * 16 + r, lane);
                }
            }
        }
    }
}

}

extern "C" void kernel_launch(void* const* d_in, const int* in_sizes, int n_in, void* d_out, int out_size) {
    (void)in_sizes; (void)n_in; (void)out_size;
    const __nv_bfloat16* q  = (const __nv_bfloat16*)d_in[0];
    const int*           qk = (const int*)d_in[1];
    const int*           qv = (const int*)d_in[2];
    const __nv_bfloat16* ks = (const __nv_bfloat16*)d_in[3];
    const __nv_bfloat16* kz = (const __nv_bfloat16*)d_in[4];
    const __nv_bfloat16* vs = (const __nv_bfloat16*)d_in[5];
    const __nv_bfloat16* vz = (const __nv_bfloat16*)d_in[6];
    __nv_bfloat16* out = (__nv_bfloat16*)d_out;

    typedef CUresult (*EncodeFn)(CUtensorMap*, CUtensorMapDataType, cuuint32_t, void*, const cuuint64_t*, const cuuint64_t*,
                                 const cuuint32_t*, const cuuint32_t*, CUtensorMapInterleave, CUtensorMapSwizzle,
                                 CUtensorMapL2promotion, CUtensorMapFloatOOBfill);
    static EncodeFn encode = nullptr;
    static int cluster = 0;
    cudaLaunchConfig_t cfg = {};
    cudaLaunchAttribute attr[1];
    cfg.gridDim = dim3(NCTA);
    cfg.blockDim = dim3(384);
    cfg.dynamicSmemBytes = SM_ALLOC;
    cfg.stream = cudaStreamPerThread;
    attr[0].id = cudaLaunchAttributeClusterDimension;
    attr[0].val.clusterDim.y = attr[0].val.clusterDim.z = 1;
    cfg.attrs = attr;
    cfg.numAttrs = 1;
    if (!encode) {
        void* fn = nullptr;
        cudaDriverEntryPointQueryResult qres;
        cudaGetDriverEntryPoint("cuTensorMapEncodeTiled", &fn, cudaEnableDefault, &qres);
        encode = (EncodeFn)fn;
        cudaFuncSetAttribute(attn_kernel<1>, cudaFuncAttributeMaxDynamicSharedMemorySize, SM_ALLOC);
        cudaFuncSetAttribute(attn_kernel<2>, cudaFuncAttributeMaxDynamicSharedMemorySize, SM_ALLOC);
        cudaFuncSetAttribute(attn_kernel<4>, cudaFuncAttributeMaxDynamicSharedMemorySize, SM_ALLOC);
        int n4 = 0, n2 = 0;
        attr[0].val.clusterDim.x = 4;
        if (cudaOccupancyMaxActiveClusters(&n4, attn_kernel<4>, &cfg) != cudaSuccess) n4 = 0;
        attr[0].val.clusterDim.x = 2;
        if (cudaOccupancyMaxActiveClusters(&n2, attn_kernel<2>, &cfg) != cudaSuccess) n2 = 0;
        (void)cudaGetLastError();
        cluster = n4 * 4 >= NCTA ? 4 : n2 * 2 >= NCTA ? 2 : 1;
    }
    CUtensorMap qmap;
    const cuuint64_t gdim[2] = {(cuuint64_t)DH, (cuuint64_t)NH * SEQ};
    const cuuint64_t gstride[1] = {(cuuint64_t)DH * 2};
    const cuuint32_t box[2] = {64, (cuuint32_t)BM};
    const cuuint32_t estride[2] = {1, 1};
    encode(&qmap, CU_TENSOR_MAP_DATA_TYPE_BFLOAT16, 2, (void*)q, gdim, gstride, box, estride, CU_TENSOR_MAP_INTERLEAVE_NONE,
           CU_TENSOR_MAP_SWIZZLE_128B, CU_TENSOR_MAP_L2_PROMOTION_L2_128B, CU_TENSOR_MAP_FLOAT_OOB_FILL_NONE);

    Params prm{q, qk, qv, ks, kz, vs, vz, out};
    attr[0].val.clusterDim.x = cluster;
    if (cluster == 4)      cudaLaunchKernelEx(&cfg, attn_kernel<4>, prm, qmap);
    else if (cluster == 2) cudaLaunchKernelEx(&cfg, attn_kernel<2>, prm, qmap);
    else                   cudaLaunchKernelEx(&cfg, attn_kernel<1>, prm, qmap);
}
```
